```python
import torch

def _softmax(x, axis=-1):
    return torch.softmax(x, dim=axis)
def _gelu(x):
    return torch.nn.functional.gelu(x, approximate="tanh")
def _silu(x):
    return torch.nn.functional.silu(x)
def _sigmoid(x):
    return torch.sigmoid(x)
def _layernorm(x, axis=-1, eps=1e-5):
    m = x.mean(dim=axis, keepdim=True)
    v = x.var(dim=axis, keepdim=True, unbiased=False)
    return (x - m) / torch.sqrt(v + eps)
def _scatter_add(tgt, idx, src, axis=0):
    return tgt.clone().index_add_(axis, idx, src)
def _segment_sum(src, seg, n):
    out = torch.zeros((n,) + src.shape[1:], dtype=src.dtype)
    return out.index_add_(0, seg, src)
def _pad(x, pw):
    flat = tuple(v for pair in reversed(pw) for v in pair)
    return torch.nn.functional.pad(x, flat)

kernel_name = 'concat_heads__gqa_block_cached__gqa_block_cached__near_ridge'

def setup_inputs():

    _w = (lambda a: (lambda t: t.to(torch.bfloat16) if t.is_floating_point() else t)(torch.as_tensor(a)))
    def _A_setup():
        B, Sq, D = 8, 96, 448
        Hq, Hkv, Sk, Dh = 16, 8, 1024, 256
        assert Hq % Hkv == 0, (Hq, Hkv)
        return {
            "x": _w((lambda *s: torch.randn(*s, dtype=torch.bfloat16) * 0.8)(B, Sq, D)),
            "k_cache": _w((lambda *s: torch.randn(*s, dtype=torch.bfloat16) * 0.8)(B, Hkv, Sk, Dh)),
            "v_cache": _w((lambda *s: torch.randn(*s, dtype=torch.bfloat16) * 0.05)(B, Hkv, Sk, Dh)),
            "wq": _w((lambda *s: torch.randn(*s, dtype=torch.bfloat16) * 0.8)(D, Hq * Dh) * (D ** -0.5)),
            "wo": _w((lambda *s: torch.randn(*s, dtype=torch.bfloat16) * 0.05)(Hq * Dh, D) * ((Hq * Dh) ** -0.5)),
        }
    _A_in = _A_setup()

    def _B_setup():
        B, Sq, D = 8, 96, 448
        Hq, Hkv, Sk, Dh = 16, 8, 1024, 256
        assert Hq % Hkv == 0, (Hq, Hkv)
        return {
            "x": _w((lambda *s: torch.randn(*s, dtype=torch.bfloat16) * 0.8)(B, Sq, D)),
            "k_cache": _w((lambda *s: torch.randn(*s, dtype=torch.bfloat16) * 0.8)(B, Hkv, Sk, Dh)),
            "v_cache": _w((lambda *s: torch.randn(*s, dtype=torch.bfloat16) * 0.05)(B, Hkv, Sk, Dh)),
            "wq": _w((lambda *s: torch.randn(*s, dtype=torch.bfloat16) * 0.8)(D, Hq * Dh) * (D ** -0.5)),
            "wo": _w((lambda *s: torch.randn(*s, dtype=torch.bfloat16) * 0.05)(Hq * Dh, D) * ((Hq * Dh) ** -0.5)),
        }
    _B_in = _B_setup()

    return {
        "A_x": _A_in["x"],
        "A_k_cache": _A_in["k_cache"],
        "A_v_cache": _A_in["v_cache"],
        "A_wq": _A_in["wq"],
        "A_wo": _A_in["wo"],
        "B_x": _B_in["x"],
        "B_k_cache": _B_in["k_cache"],
        "B_v_cache": _B_in["v_cache"],
        "B_wq": _B_in["wq"],
        "B_wo": _B_in["wo"],
    }

def reference(A_x, A_k_cache, A_v_cache, A_wq, A_wo, B_x, B_k_cache, B_v_cache, B_wq, B_wo):
    def _A_ref(x, k_cache, v_cache, wq, wo):
        B, Sq, D = x.shape
        Hq, Dh = 16, 256
        Hkv = k_cache.shape[1]
        rep = Hq // Hkv
        q = (lambda x, *d: x.permute(*d))((x @ wq).reshape(B, Sq, Hq, Dh), 0, 2, 1, 3)
        k = (lambda x, n, axis: torch.repeat_interleave(x, n, dim=axis))(k_cache, rep, axis=1)
        v = (lambda x, n, axis: torch.repeat_interleave(x, n, dim=axis))(v_cache, rep, axis=1)
        scores = torch.einsum("bhqd,bhkd->bhqk", q, k) * (Dh ** -0.5)
        p = _softmax(scores, axis=-1)
        o = torch.einsum("bhqk,bhkd->bhqd", p, v)
        return (lambda x, *d: x.permute(*d))(o, 0, 2, 1, 3).reshape(B, Sq, Hq * Dh) @ wo

    def _B_ref(x, k_cache, v_cache, wq, wo):
        B, Sq, D = x.shape
        Hq, Dh = 16, 256
        Hkv = k_cache.shape[1]
        rep = Hq // Hkv
        q = (lambda x, *d: x.permute(*d))((x @ wq).reshape(B, Sq, Hq, Dh), 0, 2, 1, 3)
        k = (lambda x, n, axis: torch.repeat_interleave(x, n, dim=axis))(k_cache, rep, axis=1)
        v = (lambda x, n, axis: torch.repeat_interleave(x, n, dim=axis))(v_cache, rep, axis=1)
        scores = torch.einsum("bhqd,bhkd->bhqk", q, k) * (Dh ** -0.5)
        p = _softmax(scores, axis=-1)
        o = torch.einsum("bhqk,bhkd->bhqd", p, v)
        return (lambda x, *d: x.permute(*d))(o, 0, 2, 1, 3).reshape(B, Sq, Hq * Dh) @ wo

    a = _A_ref(A_x, A_k_cache, A_v_cache, A_wq, A_wo)
    b = _B_ref(B_x, B_k_cache, B_v_cache, B_wq, B_wo)
    return torch.concatenate([a, b], axis=-1)
```

```cpp
#include <cuda_runtime.h>
#include <cuda_bf16.h>
#include <cuda.h>
#include <stdint.h>

namespace {

constexpr int SQ = 96, DM = 448, SK = 1024, DH = 256;
constexpr int NTHREADS = 384;

constexpr uint32_t SM_Q = 0;
constexpr uint32_t SM_RING = 98304;
constexpr uint32_t SM_BAR = SM_RING + 131072;
constexpr uint32_t BAR_FULLW = SM_BAR + 256;
constexpr uint32_t BAR_FULLKV = SM_BAR + 64;
constexpr uint32_t BAR_FULLX = SM_BAR + 104;
constexpr uint32_t BAR_EMPTYKV = SM_BAR + 208;
constexpr uint32_t BAR_OREADY = SM_BAR + 112;
constexpr uint32_t CNT_H = SM_BAR + 128;
constexpr uint32_t CNT_S = SM_BAR + 160;
constexpr uint32_t SM_EPOCH = SM_BAR + 192;
constexpr uint32_t SM_PFPOS = SM_BAR + 204;
constexpr uint32_t SM_T0 = SM_BAR + 200;
constexpr uint32_t KV_TILE = 24576;
constexpr int NT_KV = 44;
constexpr uint32_t BAR_FETCH = SM_BAR + 736;
constexpr uint32_t BAR_ACC = SM_BAR + 792;
constexpr uint32_t SMEM_BYTES = SM_BAR + 832;

struct Maps {
    CUtensorMap x[2], k[2], v[2], wq[2], wo[2], out;
    const char* kptr[2];
    const char* vptr[2];
};

__device__ __align__(1024) uint4 g_part[16 * 7 * 7 * 6 * 128];
__device__ __align__(128) unsigned int g_flag[16 * 7 * 32];
__device__ unsigned int g_epoch[128];

__device__ __forceinline__ uint32_t smem_u32(const void* p) { return (uint32_t)__cvta_generic_to_shared(p); }
__device__ __forceinline__ void mbar_init(uint32_t bar, int cnt) {
    asm volatile("mbarrier.init.shared::cta.b64 [%0], %1;" ::"r"(bar), "r"(cnt) : "memory");
}
__device__ __forceinline__ void mbar_expect_tx(uint32_t bar, uint32_t bytes) {
    asm volatile("mbarrier.arrive.expect_tx.shared::cta.b64 _, [%0], %1;" ::"r"(bar), "r"(bytes) : "memory");
}
__device__ __forceinline__ void mbar_wait(uint32_t bar, uint32_t parity) {
    asm volatile(
        "{\n.reg .pred p;\n"
        "WAIT_%=:\n"
        "mbarrier.try_wait.parity.shared::cta.b64 p, [%0], %1;\n"
        "@p bra DONE_%=;\n"
        "bra WAIT_%=;\n"
        "DONE_%=:\n}" ::"r"(bar), "r"(parity) : "memory");
}
__device__ __forceinline__ bool mbar_test(uint32_t bar, uint32_t parity) {
    uint32_t done;
    asm volatile("{\n.reg .pred p;\nmbarrier.test_wait.parity.shared::cta.b64 p, [%1], %2;\nselp.u32 %0, 1, 0, p;\n}"
                 : "=r"(done) : "r"(bar), "r"(parity) : "memory");
    return done != 0;
}
__device__ __forceinline__ void tma2d(uint32_t dst, const CUtensorMap* m, int c0, int c1, uint32_t bar) {
    asm volatile("cp.async.bulk.tensor.2d.shared::cluster.global.mbarrier::complete_tx::bytes [%0], [%1, {%3, %4}], [%2];"
                 ::"r"(dst), "l"(m), "r"(bar), "r"(c0), "r"(c1) : "memory");
}
__device__ __forceinline__ void tma3d(uint32_t dst, const CUtensorMap* m, int c0, int c1, int c2, uint32_t bar) {
    asm volatile("cp.async.bulk.tensor.3d.shared::cluster.global.mbarrier::complete_tx::bytes [%0], [%1, {%3, %4, %5}], [%2];"
                 ::"r"(dst), "l"(m), "r"(bar), "r"(c0), "r"(c1), "r"(c2) : "memory");
}
__device__ __forceinline__ void tma4d_stream(uint32_t dst, const CUtensorMap* m, int c1, int c3, uint32_t bar) {
    asm volatile("{\n.reg .b64 pol;\ncreatepolicy.fractional.L2::evict_first.b64 pol, 1.0;\n"
                 "cp.async.bulk.tensor.4d.shared::cluster.global.mbarrier::complete_tx::bytes.L2::cache_hint [%0], [%1, {0, %3, 0, %4}], [%2], pol;\n}"
                 ::"r"(dst), "l"(m), "r"(bar), "r"(c1), "r"(c3) : "memory");
}
__device__ __forceinline__ void bulk_load(uint32_t dst, const void* src, uint32_t bytes, uint32_t bar) {
    asm volatile("cp.async.bulk.shared::cluster.global.mbarrier::complete_tx::bytes [%0], [%1], %2, [%3];"
                 ::"r"(dst), "l"(src), "r"(bytes), "r"(bar) : "memory");
}
__device__ __forceinline__ void prefetch2d(const CUtensorMap* m, int c0, int c1) {
    asm volatile("cp.async.bulk.prefetch.tensor.2d.L2.global [%0, {%1, %2}];" ::"l"(m), "r"(c0), "r"(c1) : "memory");
}
__device__ __forceinline__ void prefetch_bulk(const char* p, uint32_t bytes) {
    asm volatile("cp.async.bulk.prefetch.L2.global [%0], %1;" ::"l"(p), "r"(bytes) : "memory");
}
__device__ __forceinline__ uint32_t warp_release(uint32_t addr, uint32_t v) {
    uint32_t r;
    asm volatile("{\n.reg .pred p;\nelect.sync _|p, 0xffffffff;\nmov.u32 %0, 0;\n"
                 "@p atom.relaxed.cta.shared::cta.add.u32 %0, [%1], %2;\n@p add.u32 %0, %0, %2;\n}"
                 : "=&r"(r) : "r"(addr), "r"(v) : "memory");
    return r;
}
__device__ __forceinline__ void wgmma_fence() { asm volatile("wgmma.fence.sync.aligned;" ::: "memory"); }
__device__ __forceinline__ void wgmma_commit() { asm volatile("wgmma.commit_group.sync.aligned;" ::: "memory"); }
template <int N>
__device__ __forceinline__ void wgmma_wait() { asm volatile("wgmma.wait_group.sync.aligned %0;" ::"n"(N) : "memory"); }
template <int N>
__device__ __forceinline__ void fence_regs(float (&d)[N]) {
#pragma unroll
    for (int i = 0; i < N; i++) asm volatile("" : "+f"(d[i])::"memory");
}
__device__ __forceinline__ uint32_t pack_bf16(float lo, float hi) {
    uint32_t r;
    asm("cvt.rn.bf16x2.f32 %0, %1, %2;" : "=r"(r) : "f"(hi), "f"(lo));
    return r;
}
__device__ __forceinline__ float ex2(float x) {
    float r;
    asm("ex2.approx.ftz.f32 %0, %1;" : "=f"(r) : "f"(x));
    return r;
}
__device__ __forceinline__ void stsm4(uint32_t addr, uint32_t r0, uint32_t r1, uint32_t r2, uint32_t r3) {
    asm volatile("stmatrix.sync.aligned.m8n8.x4.shared.b16 [%0], {%1, %2, %3, %4};" ::"r"(addr), "r"(r0), "r"(r1), "r"(r2), "r"(r3) : "memory");
}
__device__ __forceinline__ void stsm4_t(uint32_t addr, uint32_t r0, uint32_t r1, uint32_t r2, uint32_t r3) {
    asm volatile("stmatrix.sync.aligned.m8n8.x4.trans.shared.b16 [%0], {%1, %2, %3, %4};" ::"r"(addr), "r"(r0), "r"(r1), "r"(r2), "r"(r3) : "memory");
}
__device__ __forceinline__ void st_packet(uint4* p, uint32_t a, uint32_t b, uint32_t c, uint32_t d) {
    asm volatile("{\n.reg .b64 lo, hi;\n.reg .b128 v;\nmov.b64 lo, {%1, %2};\nmov.b64 hi, {%3, %4};\nmov.b128 v, {lo, hi};\n"
                 "st.relaxed.gpu.global.b128 [%0], v;\n}" ::"l"(p), "r"(a), "r"(b), "r"(c), "r"(d) : "memory");
}
__device__ __forceinline__ uint4 ld_packet(const uint4* p) {
    uint4 r;
    asm volatile("{\n.reg .b64 lo, hi;\n.reg .b128 v;\nld.relaxed.gpu.global.b128 v, [%4];\nmov.b128 {lo, hi}, v;\n"
                 "mov.b64 {%0, %1}, lo;\nmov.b64 {%2, %3}, hi;\n}"
                 : "=r"(r.x), "=r"(r.y), "=r"(r.z), "=r"(r.w) : "l"(p) : "memory");
    return r;
}
__device__ __forceinline__ uint32_t make_desc(uint32_t addr, uint32_t lbo_bytes) {
    return (addr >> 4) | ((lbo_bytes >> 4) << 16);
}
__device__ __forceinline__ void warp_arrive(uint32_t bar) {
    asm volatile("{\n.reg .pred p;\nelect.sync _|p, 0xffffffff;\n@p mbarrier.arrive.shared::cta.b64 _, [%0];\n}" ::"r"(bar) : "memory");
}
__device__ __forceinline__ bool elect_one() {
    uint32_t r;
    asm volatile("{\n.reg .pred p;\nelect.sync _|p, 0xffffffff;\nselp.u32 %0, 1, 0, p;\n}" : "=r"(r));
    return r != 0;
}
#define BAR_SYNC(id, n) asm volatile("bar.sync %0, %1;" ::"r"(id), "n"(n) : "memory")
#define BAR_ARRIVE(id, n) asm volatile("bar.arrive %0, %1;" ::"r"(id), "n"(n) : "memory")

__device__ __forceinline__ void wgmma_n48_ss_first(float (&d)[24], uint64_t da, uint64_t db) {
    asm volatile(
        "wgmma.mma_async.sync.aligned.m64n48k16.f32.bf16.bf16 {"
        "%0, %1, %2, %3, %4, %5, %6, %7, %8, %9, %10, %11, %12, %13, %14, %15, %16, %17, %18, %19, %20, %21, %22, %23"
        "}, %24, %25, 0, 1, 1, 0, 0;\n"
        : "=f"(d[0]), "=f"(d[1]), "=f"(d[2]), "=f"(d[3]), "=f"(d[4]), "=f"(d[5]), "=f"(d[6]), "=f"(d[7]), "=f"(d[8]),
          "=f"(d[9]), "=f"(d[10]), "=f"(d[11]), "=f"(d[12]), "=f"(d[13]), "=f"(d[14]), "=f"(d[15]), "=f"(d[16]),
          "=f"(d[17]), "=f"(d[18]), "=f"(d[19]), "=f"(d[20]), "=f"(d[21]), "=f"(d[22]), "=f"(d[23])
        : "l"(da), "l"(db));
}
__device__ __forceinline__ void wgmma_n48_ss(float (&d)[24], uint64_t da, uint64_t db) {
    asm volatile(
        "wgmma.mma_async.sync.aligned.m64n48k16.f32.bf16.bf16 {"
        "%0, %1, %2, %3, %4, %5, %6, %7, %8, %9, %10, %11, %12, %13, %14, %15, %16, %17, %18, %19, %20, %21, %22, %23"
        "}, %24, %25, 1, 1, 1, 0, 0;\n"
        : "+f"(d[0]), "+f"(d[1]), "+f"(d[2]), "+f"(d[3]), "+f"(d[4]), "+f"(d[5]), "+f"(d[6]), "+f"(d[7]), "+f"(d[8]),
          "+f"(d[9]), "+f"(d[10]), "+f"(d[11]), "+f"(d[12]), "+f"(d[13]), "+f"(d[14]), "+f"(d[15]), "+f"(d[16]),
          "+f"(d[17]), "+f"(d[18]), "+f"(d[19]), "+f"(d[20]), "+f"(d[21]), "+f"(d[22]), "+f"(d[23])
        : "l"(da), "l"(db));
}
__device__ __forceinline__ void wgmma_n16_ss_first(float (&d)[8], uint32_t da, uint32_t db) {
    asm volatile(
        "{\n.reg .b64 da, db;\nmov.b64 da, {%8, 0x40000040};\nmov.b64 db, {%9, 0x40000040};\n"
        "wgmma.mma_async.sync.aligned.m64n16k16.f32.bf16.bf16 {"
        "%0, %1, %2, %3, %4, %5, %6, %7"
        "}, da, db, 0, 1, 1, 0, 0;\n}\n"
        : "=f"(d[0]), "=f"(d[1]), "=f"(d[2]), "=f"(d[3]), "=f"(d[4]), "=f"(d[5]), "=f"(d[6]), "=f"(d[7])
        : "r"(da), "r"(db));
}
__device__ __forceinline__ void wgmma_n16_ss(float (&d)[8], uint32_t da, uint32_t db) {
    asm volatile(
        "{\n.reg .b64 da, db;\nmov.b64 da, {%8, 0x40000040};\nmov.b64 db, {%9, 0x40000040};\n"
        "wgmma.mma_async.sync.aligned.m64n16k16.f32.bf16.bf16 {"
        "%0, %1, %2, %3, %4, %5, %6, %7"
        "}, da, db, 1, 1, 1, 0, 0;\n}\n"
        : "+f"(d[0]), "+f"(d[1]), "+f"(d[2]), "+f"(d[3]), "+f"(d[4]), "+f"(d[5]), "+f"(d[6]), "+f"(d[7])
        : "r"(da), "r"(db));
}
__device__ __forceinline__ void wgmma_n96_ta_first(float (&d)[48], uint32_t da, uint32_t db) {
    asm volatile(
        "{\n.reg .b64 da, db;\nmov.b64 da, {%48, 0x40000040};\nmov.b64 db, {%49, 0x40000040};\n"
        "wgmma.mma_async.sync.aligned.m64n96k16.f32.bf16.bf16 {"
        "%0, %1, %2, %3, %4, %5, %6, %7, %8, %9, %10, %11, %12, %13, %14, %15, %16, %17, %18, %19, %20, %21, %22, %23, "
        "%24, %25, %26, %27, %28, %29, %30, %31, %32, %33, %34, %35, %36, %37, %38, %39, %40, %41, %42, %43, %44, %45, "
        "%46, %47"
        "}, da, db, 0, 1, 1, 1, 0;\n}\n"
        : "=f"(d[0]), "=f"(d[1]), "=f"(d[2]), "=f"(d[3]), "=f"(d[4]), "=f"(d[5]), "=f"(d[6]), "=f"(d[7]), "=f"(d[8]),
          "=f"(d[9]), "=f"(d[10]), "=f"(d[11]), "=f"(d[12]), "=f"(d[13]), "=f"(d[14]), "=f"(d[15]), "=f"(d[16]),
          "=f"(d[17]), "=f"(d[18]), "=f"(d[19]), "=f"(d[20]), "=f"(d[21]), "=f"(d[22]), "=f"(d[23]), "=f"(d[24]),
          "=f"(d[25]), "=f"(d[26]), "=f"(d[27]), "=f"(d[28]), "=f"(d[29]), "=f"(d[30]), "=f"(d[31]), "=f"(d[32]),
          "=f"(d[33]), "=f"(d[34]), "=f"(d[35]), "=f"(d[36]), "=f"(d[37]), "=f"(d[38]), "=f"(d[39]), "=f"(d[40]),
          "=f"(d[41]), "=f"(d[42]), "=f"(d[43]), "=f"(d[44]), "=f"(d[45]), "=f"(d[46]), "=f"(d[47])
        : "r"(da), "r"(db));
}
__device__ __forceinline__ void wgmma_n96_ta(float (&d)[48], uint32_t da, uint32_t db) {
    asm volatile(
        "{\n.reg .b64 da, db;\nmov.b64 da, {%48, 0x40000040};\nmov.b64 db, {%49, 0x40000040};\n"
        "wgmma.mma_async.sync.aligned.m64n96k16.f32.bf16.bf16 {"
        "%0, %1, %2, %3, %4, %5, %6, %7, %8, %9, %10, %11, %12, %13, %14, %15, %16, %17, %18, %19, %20, %21, %22, %23, "
        "%24, %25, %26, %27, %28, %29, %30, %31, %32, %33, %34, %35, %36, %37, %38, %39, %40, %41, %42, %43, %44, %45, "
        "%46, %47"
        "}, da, db, 1, 1, 1, 1, 0;\n}\n"
        : "+f"(d[0]), "+f"(d[1]), "+f"(d[2]), "+f"(d[3]), "+f"(d[4]), "+f"(d[5]), "+f"(d[6]), "+f"(d[7]), "+f"(d[8]),
          "+f"(d[9]), "+f"(d[10]), "+f"(d[11]), "+f"(d[12]), "+f"(d[13]), "+f"(d[14]), "+f"(d[15]), "+f"(d[16]),
          "+f"(d[17]), "+f"(d[18]), "+f"(d[19]), "+f"(d[20]), "+f"(d[21]), "+f"(d[22]), "+f"(d[23]), "+f"(d[24]),
          "+f"(d[25]), "+f"(d[26]), "+f"(d[27]), "+f"(d[28]), "+f"(d[29]), "+f"(d[30]), "+f"(d[31]), "+f"(d[32]),
          "+f"(d[33]), "+f"(d[34]), "+f"(d[35]), "+f"(d[36]), "+f"(d[37]), "+f"(d[38]), "+f"(d[39]), "+f"(d[40]),
          "+f"(d[41]), "+f"(d[42]), "+f"(d[43]), "+f"(d[44]), "+f"(d[45]), "+f"(d[46]), "+f"(d[47])
        : "r"(da), "r"(db));
}
__device__ __forceinline__ void wgmma_n232_rs(float (&d)[116], uint32_t a0, uint32_t a1, uint32_t a2, uint32_t a3, uint32_t db) {
    asm volatile(
        "{\n.reg .b64 db;\nmov.b64 db, {%120, 0x40000040};\n"
        "wgmma.mma_async.sync.aligned.m64n232k16.f32.bf16.bf16 {"
        "%0, %1, %2, %3, %4, %5, %6, %7, %8, %9, %10, %11, %12, %13, %14, %15, %16, %17, %18, %19, %20, %21, %22, %23, "
        "%24, %25, %26, %27, %28, %29, %30, %31, %32, %33, %34, %35, %36, %37, %38, %39, %40, %41, %42, %43, %44, %45, "
        "%46, %47, %48, %49, %50, %51, %52, %53, %54, %55, %56, %57, %58, %59, %60, %61, %62, %63, %64, %65, %66, %67, "
        "%68, %69, %70, %71, %72, %73, %74, %75, %76, %77, %78, %79, %80, %81, %82, %83, %84, %85, %86, %87, %88, %89, "
        "%90, %91, %92, %93, %94, %95, %96, %97, %98, %99, %100, %101, %102, %103, %104, %105, %106, %107, %108, %109, "
        "%110, %111, %112, %113, %114, %115"
        "}, {%116, %117, %118, %119}, db, 1, 1, 1, 1;\n}\n"
        : "+f"(d[0]), "+f"(d[1]), "+f"(d[2]), "+f"(d[3]), "+f"(d[4]), "+f"(d[5]), "+f"(d[6]), "+f"(d[7]), "+f"(d[8]),
          "+f"(d[9]), "+f"(d[10]), "+f"(d[11]), "+f"(d[12]), "+f"(d[13]), "+f"(d[14]), "+f"(d[15]), "+f"(d[16]),
          "+f"(d[17]), "+f"(d[18]), "+f"(d[19]), "+f"(d[20]), "+f"(d[21]), "+f"(d[22]), "+f"(d[23]), "+f"(d[24]),
          "+f"(d[25]), "+f"(d[26]), "+f"(d[27]), "+f"(d[28]), "+f"(d[29]), "+f"(d[30]), "+f"(d[31]), "+f"(d[32]),
          "+f"(d[33]), "+f"(d[34]), "+f"(d[35]), "+f"(d[36]), "+f"(d[37]), "+f"(d[38]), "+f"(d[39]), "+f"(d[40]),
          "+f"(d[41]), "+f"(d[42]), "+f"(d[43]), "+f"(d[44]), "+f"(d[45]), "+f"(d[46]), "+f"(d[47]), "+f"(d[48]),
          "+f"(d[49]), "+f"(d[50]), "+f"(d[51]), "+f"(d[52]), "+f"(d[53]), "+f"(d[54]), "+f"(d[55]), "+f"(d[56]),
          "+f"(d[57]), "+f"(d[58]), "+f"(d[59]), "+f"(d[60]), "+f"(d[61]), "+f"(d[62]), "+f"(d[63]), "+f"(d[64]),
          "+f"(d[65]), "+f"(d[66]), "+f"(d[67]), "+f"(d[68]), "+f"(d[69]), "+f"(d[70]), "+f"(d[71]), "+f"(d[72]),
          "+f"(d[73]), "+f"(d[74]), "+f"(d[75]), "+f"(d[76]), "+f"(d[77]), "+f"(d[78]), "+f"(d[79]), "+f"(d[80]),
          "+f"(d[81]), "+f"(d[82]), "+f"(d[83]), "+f"(d[84]), "+f"(d[85]), "+f"(d[86]), "+f"(d[87]), "+f"(d[88]),
          "+f"(d[89]), "+f"(d[90]), "+f"(d[91]), "+f"(d[92]), "+f"(d[93]), "+f"(d[94]), "+f"(d[95]), "+f"(d[96]),
          "+f"(d[97]), "+f"(d[98]), "+f"(d[99]), "+f"(d[100]), "+f"(d[101]), "+f"(d[102]), "+f"(d[103]), "+f"(d[104]),
          "+f"(d[105]), "+f"(d[106]), "+f"(d[107]), "+f"(d[108]), "+f"(d[109]), "+f"(d[110]), "+f"(d[111]),
          "+f"(d[112]), "+f"(d[113]), "+f"(d[114]), "+f"(d[115])
        : "r"(a0), "r"(a1), "r"(a2), "r"(a3), "r"(db));
}
__device__ __forceinline__ void wgmma_n232_rs_first(float (&d)[116], uint32_t a0, uint32_t a1, uint32_t a2, uint32_t a3, uint32_t db) {
    asm volatile(
        "{\n.reg .b64 db;\nmov.b64 db, {%120, 0x40000040};\n"
        "wgmma.mma_async.sync.aligned.m64n232k16.f32.bf16.bf16 {"
        "%0, %1, %2, %3, %4, %5, %6, %7, %8, %9, %10, %11, %12, %13, %14, %15, %16, %17, %18, %19, %20, %21, %22, %23, "
        "%24, %25, %26, %27, %28, %29, %30, %31, %32, %33, %34, %35, %36, %37, %38, %39, %40, %41, %42, %43, %44, %45, "
        "%46, %47, %48, %49, %50, %51, %52, %53, %54, %55, %56, %57, %58, %59, %60, %61, %62, %63, %64, %65, %66, %67, "
        "%68, %69, %70, %71, %72, %73, %74, %75, %76, %77, %78, %79, %80, %81, %82, %83, %84, %85, %86, %87, %88, %89, "
        "%90, %91, %92, %93, %94, %95, %96, %97, %98, %99, %100, %101, %102, %103, %104, %105, %106, %107, %108, %109, "
        "%110, %111, %112, %113, %114, %115"
        "}, {%116, %117, %118, %119}, db, 0, 1, 1, 1;\n}\n"
        : "=&f"(d[0]), "=&f"(d[1]), "=&f"(d[2]), "=&f"(d[3]), "=&f"(d[4]), "=&f"(d[5]), "=&f"(d[6]), "=&f"(d[7]),
          "=&f"(d[8]), "=&f"(d[9]), "=&f"(d[10]), "=&f"(d[11]), "=&f"(d[12]), "=&f"(d[13]), "=&f"(d[14]), "=&f"(d[15]),
          "=&f"(d[16]), "=&f"(d[17]), "=&f"(d[18]), "=&f"(d[19]), "=&f"(d[20]), "=&f"(d[21]), "=&f"(d[22]),
          "=&f"(d[23]), "=&f"(d[24]), "=&f"(d[25]), "=&f"(d[26]), "=&f"(d[27]), "=&f"(d[28]), "=&f"(d[29]),
          "=&f"(d[30]), "=&f"(d[31]), "=&f"(d[32]), "=&f"(d[33]), "=&f"(d[34]), "=&f"(d[35]), "=&f"(d[36]),
          "=&f"(d[37]), "=&f"(d[38]), "=&f"(d[39]), "=&f"(d[40]), "=&f"(d[41]), "=&f"(d[42]), "=&f"(d[43]),
          "=&f"(d[44]), "=&f"(d[45]), "=&f"(d[46]), "=&f"(d[47]), "=&f"(d[48]), "=&f"(d[49]), "=&f"(d[50]),
          "=&f"(d[51]), "=&f"(d[52]), "=&f"(d[53]), "=&f"(d[54]), "=&f"(d[55]), "=&f"(d[56]), "=&f"(d[57]),
          "=&f"(d[58]), "=&f"(d[59]), "=&f"(d[60]), "=&f"(d[61]), "=&f"(d[62]), "=&f"(d[63]), "=&f"(d[64]),
          "=&f"(d[65]), "=&f"(d[66]), "=&f"(d[67]), "=&f"(d[68]), "=&f"(d[69]), "=&f"(d[70]), "=&f"(d[71]),
          "=&f"(d[72]), "=&f"(d[73]), "=&f"(d[74]), "=&f"(d[75]), "=&f"(d[76]), "=&f"(d[77]), "=&f"(d[78]),
          "=&f"(d[79]), "=&f"(d[80]), "=&f"(d[81]), "=&f"(d[82]), "=&f"(d[83]), "=&f"(d[84]), "=&f"(d[85]),
          "=&f"(d[86]), "=&f"(d[87]), "=&f"(d[88]), "=&f"(d[89]), "=&f"(d[90]), "=&f"(d[91]), "=&f"(d[92]),
          "=&f"(d[93]), "=&f"(d[94]), "=&f"(d[95]), "=&f"(d[96]), "=&f"(d[97]), "=&f"(d[98]), "=&f"(d[99]),
          "=&f"(d[100]), "=&f"(d[101]), "=&f"(d[102]), "=&f"(d[103]), "=&f"(d[104]), "=&f"(d[105]), "=&f"(d[106]),
          "=&f"(d[107]), "=&f"(d[108]), "=&f"(d[109]), "=&f"(d[110]), "=&f"(d[111]), "=&f"(d[112]), "=&f"(d[113]),
          "=&f"(d[114]), "=&f"(d[115])
        : "r"(a0), "r"(a1), "r"(a2), "r"(a3), "r"(db));
}
__device__ __forceinline__ void wgmma_n24_rs(float (&d)[12], uint32_t a0, uint32_t a1, uint32_t a2, uint32_t a3, uint32_t db) {
    asm volatile(
        "{\n.reg .b64 db;\nmov.b64 db, {%16, 0x40000040};\n"
        "wgmma.mma_async.sync.aligned.m64n24k16.f32.bf16.bf16 {"
        "%0, %1, %2, %3, %4, %5, %6, %7, %8, %9, %10, %11"
        "}, {%12, %13, %14, %15}, db, 1, 1, 1, 1;\n}\n"
        : "+f"(d[0]), "+f"(d[1]), "+f"(d[2]), "+f"(d[3]), "+f"(d[4]), "+f"(d[5]), "+f"(d[6]), "+f"(d[7]), "+f"(d[8]),
          "+f"(d[9]), "+f"(d[10]), "+f"(d[11])
        : "r"(a0), "r"(a1), "r"(a2), "r"(a3), "r"(db));
}
__device__ __forceinline__ void wgmma_n24_rs_first(float (&d)[12], uint32_t a0, uint32_t a1, uint32_t a2, uint32_t a3, uint32_t db) {
    asm volatile(
        "{\n.reg .b64 db;\nmov.b64 db, {%16, 0x40000040};\n"
        "wgmma.mma_async.sync.aligned.m64n24k16.f32.bf16.bf16 {"
        "%0, %1, %2, %3, %4, %5, %6, %7, %8, %9, %10, %11"
        "}, {%12, %13, %14, %15}, db, 0, 1, 1, 1;\n}\n"
        : "=&f"(d[0]), "=&f"(d[1]), "=&f"(d[2]), "=&f"(d[3]), "=&f"(d[4]), "=&f"(d[5]), "=&f"(d[6]), "=&f"(d[7]),
          "=&f"(d[8]), "=&f"(d[9]), "=&f"(d[10]), "=&f"(d[11])
        : "r"(a0), "r"(a1), "r"(a2), "r"(a3), "r"(db));
}

constexpr int PF_T0 = 2800;
constexpr int PF_DT = 170;
constexpr int PF_N = 38;
constexpr int PF_LASTW = 24;
constexpr int PF_CH = 4096, PF_F = 5, PF_MAXB = 4;
constexpr int TH_A = 8200;
constexpr int TH_D = 828;
constexpr int HEADSTART = 700;
constexpr int LAG_X = 34;
constexpr int PROD_WARP = 4;
constexpr int RATE_SH = 4;
constexpr int WO_EVENT = 41;

template <int N>
struct IC { static constexpr int value = N; };

__global__ void __launch_bounds__(NTHREADS, 1)
fused_gqa_kernel(const __grid_constant__ Maps maps) {
    extern __shared__ __align__(1024) uint8_t smem[];
    const uint32_t sb = smem_u32(smem);
    const int tid = threadIdx.x;
    const int warp = __shfl_sync(0xffffffffu, tid >> 5, 0);
    const int wg = warp >> 2, wi = warp & 3;
    const int bar_me = 4 + wg, bar_next = 4 + (wg == 2 ? 0 : wg + 1);
    const int lane = tid & 31;
    const int blk = blockIdx.x >> 6, kvh = (blockIdx.x >> 3) & 7, b = blockIdx.x & 7;
    const int head = b * 8 + kvh;
    const CUtensorMap* mK = &maps.k[blk];
    const CUtensorMap* mV = &maps.v[blk];
    const CUtensorMap* mWq = &maps.wq[blk];
    const CUtensorMap* mWo = &maps.wo[blk];

    auto otile = [&](int s) {
        const int r = s + (kvh == 7 ? 0 : kvh + 1);
        return r >= 7 ? r - 7 : r;
    };
    auto issue_wq = [&](int w) {
        const uint32_t bar = sb + BAR_FULLW + w * 8;
        mbar_expect_tx(bar, 14336);
        tma2d(sb + SM_RING + (w & 7) * 16384, mWq, kvh * 512 + (w >> 2) * 64, (w & 3) * 112, bar);
    };
    auto issue_wo = [&](int p) {
        const uint32_t h = (p + 6) & 7;
        const uint32_t bar = sb + BAR_FULLW + (32 + p) * 8;
        mbar_expect_tx(bar, 16384);
        tma2d(sb + SM_RING + h * 16384, mWo, otile(p >> 2) * 64, kvh * 512 + (p & 3) * 128, bar);
    };
    auto issue_kv = [&](int t, uint32_t slot) {
        const uint32_t bar = sb + BAR_FULLKV + slot * 8;
        mbar_expect_tx(bar, KV_TILE);
        tma4d_stream(sb + SM_RING + slot * KV_TILE, (t & 1) ? mV : mK, (t >> 1) * 48 - 32, head, bar);
    };

    auto prefetch_kv = [&]() {
        if (elect_one()) {
            uint32_t now, t0;
            int c;
            asm volatile("mov.u32 %0, %%globaltimer_lo;" : "=r"(now));
            asm volatile("ld.volatile.shared.v2.u32 {%0, %1}, [%2];" : "=r"(t0), "=r"(c) : "r"(sb + SM_T0));
            int ce = ((int)(now - t0) - PF_T0) / PF_DT + 1;
            ce = min(min(ce, PF_N), c + PF_MAXB);
            if (ce > c) {
                asm volatile("atom.shared.max.s32 %0, [%1], %2;" : "=r"(c) : "r"(sb + SM_PFPOS), "r"(ce) : "memory");
#pragma unroll 1
                for (; c < ce; c++) {
                    const int t = PF_F + c;
                    const char* base = (t & 1) ? maps.vptr[blk] : maps.kptr[blk];
                    prefetch_bulk(base + (size_t)head * (SK * DH * 2) + ((t >> 1) * 48 - 32) * 512, PF_CH);
                }
            }
        }
        __syncwarp();
    };

    if (wg == 1) {
        const char* base = ((wi & 1) ? maps.vptr[blk] : maps.kptr[blk]) + (size_t)head * (SK * DH * 2) + (wi >> 1) * 4096;
        asm volatile("prefetch.global.L2 [%0];" ::"l"(base + lane * 128));
    }
    if (tid < 32) {
        if (elect_one()) {
            uint32_t now;
            asm volatile("mov.u32 %0, %%globaltimer_lo;" : "=r"(now));
            asm volatile("st.shared.u32 [%0], %1;" ::"r"(sb + SM_T0), "r"(now) : "memory");
            mbar_init(sb + BAR_FULLW, 1);
            mbar_init(sb + BAR_FULLX, 1);
            issue_wq(0);
            mbar_expect_tx(sb + BAR_FULLX, 86016);
            tma3d(sb + SM_Q, &maps.x[blk], 0, b * SQ, 0, sb + BAR_FULLX);
#pragma unroll
            for (int w = 1; w < 8; w++) mbar_init(sb + BAR_FULLW + w * 8, 1);
#pragma unroll
            for (int w = 1; w < 8; w++) issue_wq(w);
#pragma unroll
            for (int i = 0; i < 3; i++) {
                const int w = 8 + b + 8 * i;
                prefetch2d(mWq, kvh * 512 + (w >> 2) * 64, (w & 3) * 112);
            }
        }
        __syncwarp();
    }
    if (tid == 160) {
        if (sb & 1023) __trap();
#pragma unroll
        for (int i = 0; i < 5; i++) {
            mbar_init(sb + BAR_FULLKV + i * 8, 1);
            mbar_init(sb + BAR_EMPTYKV + i * 8, 12);
        }
        mbar_init(sb + BAR_OREADY, 6);
        mbar_init(sb + BAR_OREADY + 8, 6);
        mbar_init(sb + BAR_ACC, 4);
        asm volatile("fence.mbarrier_init.release.cluster;" ::: "memory");
    } else if (tid >= 64 && tid < 64 + 59) {
        mbar_init(sb + BAR_FULLW + (tid - 56) * 8, 1);
        asm volatile("fence.mbarrier_init.release.cluster;" ::: "memory");
    } else if (tid == 128) {
#pragma unroll
        for (int i = 0; i < 13; i++) asm volatile("st.shared.u32 [%0], %1;" ::"r"(sb + CNT_H + i * 4), "r"(0) : "memory");
        asm volatile("st.shared.u32 [%0], %1;" ::"r"(sb + SM_PFPOS), "r"(0) : "memory");
    }
    __syncthreads();
    unsigned int epoch_prev = 0;
    if (tid == 320) asm volatile("ld.global.u32 %0, [%1];" : "=r"(epoch_prev) : "l"(g_epoch + blockIdx.x) : "memory");

    {
        uint32_t qa[24], qb[24], qc[24];
#pragma unroll
        for (int r = 0; r < 24; r++) qa[r] = qb[r] = 0;
        mbar_wait(sb + BAR_FULLX, 0);
#pragma unroll 1
        for (int i = wg; i < 8; i += 3) {
            float acc[48];
            auto release = [&](int w) {
                if (w < 24) {
                    if (warp_release(sb + CNT_H + (w & 7) * 4, 1) == 4 * ((w >> 3) + 1)) issue_wq(w + 8);
                } else if (w != 24 && w != 30) {
                    const int t = w < 28 ? w - 25 : (w == 31 ? 4 : w - 26);
                    if (warp_release(sb + CNT_S + t * 4, t == 2 ? 3 : 6) == 24) issue_kv(t, t);
                }
                if (wi == 1 && w <= PF_LASTW) prefetch_kv();
            };
            if (i > 0) BAR_SYNC(bar_me, 256);
#pragma unroll
            for (int qd = 0; qd < 4; qd++) {
                const int w = 4 * i + qd;
                mbar_wait(sb + BAR_FULLW + w * 8, 0);
                const uint32_t da = make_desc(sb + SM_RING + (w & 7) * 16384, 0);
                const uint32_t db = make_desc(sb + SM_Q, 0);
                wgmma_fence();
#pragma unroll
                for (int ks = 0; ks < 7; ks++) {
                    const int kk = qd * 7 + ks;
                    const uint32_t a = da + ((ks * 2048) >> 4);
                    const uint32_t bb = db + (((kk >> 2) * 12288 + (kk & 3) * 32) >> 4);
                    if (kk == 0) wgmma_n96_ta_first(acc, a, bb);
                    else wgmma_n96_ta(acc, a, bb);
                }
                wgmma_commit();
                if (qd == 2 && i < 7) BAR_ARRIVE(bar_next, 256);
                if (qd > 0) {
                    wgmma_wait<1>();
                    release(w - 1);
                }
            }
            wgmma_wait<0>();
            fence_regs(acc);
            release(4 * i + 3);
#pragma unroll
            for (int r = 0; r < 24; r++) {
                qc[r] = qb[r];
                qb[r] = qa[r];
                qa[r] = pack_bf16(acc[2 * r], acc[2 * r + 1]);
            }
        }
        if (warp == 9) {
            while (true) {
                prefetch_kv();
                if (mbar_test(sb + BAR_FULLW + 31 * 8, 0)) break;
                __nanosleep(64);
            }
        }
        if (tid == 320) {
            asm volatile("st.shared.u32 [%0], %1;" ::"r"(sb + SM_EPOCH), "r"(epoch_prev + 1) : "memory");
        }
        __syncthreads();
        {
            const int mi = lane >> 3, r = lane & 7;
            const uint32_t base = sb + SM_Q + ((mi >> 1) * 8 + r) * 128 + (((2 * wi + (mi & 1)) ^ r) << 4);
            auto put = [&](const uint32_t (&q)[24], int i) {
                const uint32_t a = base + (i & 3) * 24576 + (i >> 2) * 12288;
#pragma unroll
                for (int j = 0; j < 12; j += 2) stsm4_t(a + j * 1024, q[2 * j], q[2 * j + 1], q[2 * j + 2], q[2 * j + 3]);
            };
            const int il = wg == 2 ? 5 : wg + 6;
            put(qa, il);
            put(qb, il - 3);
            if (wg != 2) put(qc, il - 6);
        }
        asm volatile("fence.proxy.async.shared::cta;" ::: "memory");
        __syncthreads();
        if (warp == 9) prefetch_kv();
    }
    if (tid == 320) g_epoch[blockIdx.x] = epoch_prev + 1;

    {
        constexpr float SC = 0.0625f * 1.4426950408889634f;
        constexpr float RESCALE_T = 10.f;
        float oa[116], ob[12];
        float m0, m1, l0, l1;
        const uint32_t dq = make_desc(sb + SM_Q + wg * 8192, 0);
        constexpr uint32_t VB_OFF = 3 * 6144 + (232 - 192) * 2;

        uint32_t tbase;
        asm volatile("ld.shared.u32 %0, [%1];" : "=r"(tbase) : "r"(sb + SM_T0));
        tbase = __shfl_sync(0xffffffffu, tbase, 0) + TH_A + 5 * TH_D - (kvh == 7 ? HEADSTART : 0);
        int lag = 0;
        auto produce = [&](int t) {
            if (warp == PROD_WARP) {
                const int tt = t - (t > LAG_X);
                if (tt < NT_KV - 5 && t != LAG_X + 1) {
                    const uint32_t use = (uint32_t)tt / 5u, slot = (uint32_t)tt - use * 5u;
                    mbar_wait(sb + BAR_EMPTYKV + slot * 8, use & 1);
                    const uint32_t due = tbase + tt * TH_D + lag;
                    uint32_t now;
#pragma unroll 1
                    for (int it = 0; it < 256; it++) {
                        asm volatile("mov.u32 %0, %%globaltimer_lo;" : "=r"(now));
                        if ((int)(now - due) >= 0) break;
                    }
                    if (tt >= 6) {
                        const int late = (int)(now - due) + lag;
                        lag = max(0, late - (late >> RATE_SH));
                    }
                    if (elect_one()) issue_kv(tt + 5, slot);
                    __syncwarp();
                } else if (t == WO_EVENT) {
                    mbar_wait(sb + BAR_EMPTYKV + (WO_EVENT % 5) * 8, (WO_EVENT / 5) & 1);
                    if (elect_one()) {
#pragma unroll
                        for (int p = 0; p < 5; p++) issue_wo(p);
                    }
                    __syncwarp();
                }
            }
        };

        if (wg == 2) BAR_ARRIVE(4, 256);
        {
            float s[8];
            mbar_wait(sb + BAR_FULLKV, 0);
            const uint32_t dk = make_desc(sb + SM_RING + 4096, 0);
            BAR_SYNC(bar_me, 256);
            wgmma_fence();
#pragma unroll
            for (int kk = 0; kk < 16; kk++) {
                const uint32_t a = dq + (((kk >> 2) * 24576 + (kk & 3) * 32) >> 4);
                const uint32_t bb = dk + (((kk >> 2) * 6144 + (kk & 3) * 32) >> 4);
                if (kk == 0) wgmma_n16_ss_first(s, a, bb);
                else wgmma_n16_ss(s, a, bb);
            }
            wgmma_commit();
            BAR_ARRIVE(bar_next, 256);
            wgmma_wait<0>();
            fence_regs(s);
            warp_arrive(sb + BAR_EMPTYKV);
            m0 = fmaxf(fmaxf(s[0], s[1]), fmaxf(s[4], s[5]));
            m1 = fmaxf(fmaxf(s[2], s[3]), fmaxf(s[6], s[7]));
            m0 = fmaxf(m0, __shfl_xor_sync(0xffffffffu, m0, 1));
            m1 = fmaxf(m1, __shfl_xor_sync(0xffffffffu, m1, 1));
            m0 = fmaxf(m0, __shfl_xor_sync(0xffffffffu, m0, 2)) * SC;
            m1 = fmaxf(m1, __shfl_xor_sync(0xffffffffu, m1, 2)) * SC;
#pragma unroll
            for (int i = 0; i < 8; i++) s[i] = ex2(fmaf(s[i], SC, (i & 2) ? -m1 : -m0));
            l0 = (s[0] + s[1]) + (s[4] + s[5]);
            l1 = (s[2] + s[3]) + (s[6] + s[7]);
            const uint32_t p0 = pack_bf16(s[0], s[1]), p1 = pack_bf16(s[2], s[3]), p2 = pack_bf16(s[4], s[5]), p3 = pack_bf16(s[6], s[7]);
            mbar_wait(sb + BAR_FULLKV + 8, 0);
            const uint32_t dv = make_desc(sb + SM_RING + KV_TILE + 4096, 6144);
            float tb[12];
            wgmma_fence();
            wgmma_n24_rs_first(tb, p0, p1, p2, p3, dv + (VB_OFF >> 4));
            wgmma_n232_rs_first(oa, p0, p1, p2, p3, dv);
            wgmma_commit();
            produce(0);
            wgmma_wait<0>();
            fence_regs(oa);
            fence_regs(tb);
            warp_arrive(sb + BAR_EMPTYKV + 8);
#pragma unroll
            for (int i = 0; i < 12; i++) ob[i] = tb[i] + 0.f;
        }

        uint32_t slot = 2, use = 0;
#pragma unroll 1
        for (int t = 2; t < NT_KV; t += 2) {
            float s[24];
            mbar_wait(sb + BAR_FULLKV + slot * 8, use & 1);
            {
                const uint32_t dk = make_desc(sb + SM_RING + slot * KV_TILE, 0);
                uint64_t da64 = 0x4000004000000000ull | (dq + (use >> 8)), db64 = 0x4000004000000000ull | dk;
                BAR_SYNC(bar_me, 256);
                wgmma_fence();
#pragma unroll
                for (int kk = 0; kk < 16; kk++) {
                    const uint64_t a = da64 + (((kk >> 2) * 24576 + (kk & 3) * 32) >> 4);
                    const uint64_t bb = db64 + (((kk >> 2) * 6144 + (kk & 3) * 32) >> 4);
                    if (kk == 0) wgmma_n48_ss_first(s, a, bb);
                    else wgmma_n48_ss(s, a, bb);
                }
                wgmma_commit();
                BAR_ARRIVE(bar_next, 256);
                produce(t - 1);
                wgmma_wait<0>();
                fence_regs(s);
            }
            warp_arrive(sb + BAR_EMPTYKV + slot * 8);
            if (++slot == 5) { slot = 0; use++; }

#pragma unroll
            for (int i = 0; i < 24; i++) s[i] = fmaf(s[i], SC, (i & 2) ? -m1 : -m0);
            float z0 = fmaxf(fmaxf(fmaxf(s[0], s[1]), fmaxf(s[4], s[5])), fmaxf(fmaxf(s[8], s[9]), fmaxf(s[12], s[13])));
            z0 = fmaxf(z0, fmaxf(fmaxf(s[16], s[17]), fmaxf(s[20], s[21])));
            float z1 = fmaxf(fmaxf(fmaxf(s[2], s[3]), fmaxf(s[6], s[7])), fmaxf(fmaxf(s[10], s[11]), fmaxf(s[14], s[15])));
            z1 = fmaxf(z1, fmaxf(fmaxf(s[18], s[19]), fmaxf(s[22], s[23])));
            if (__any_sync(0xffffffffu, fmaxf(z0, z1) > RESCALE_T)) {
                z0 = fmaxf(z0, __shfl_xor_sync(0xffffffffu, z0, 1));
                z1 = fmaxf(z1, __shfl_xor_sync(0xffffffffu, z1, 1));
                z0 = fmaxf(fmaxf(z0, __shfl_xor_sync(0xffffffffu, z0, 2)), 0.f);
                z1 = fmaxf(fmaxf(z1, __shfl_xor_sync(0xffffffffu, z1, 2)), 0.f);
                const float n0 = m0 + z0, n1 = m1 + z1;
                z0 = n0 - m0;
                z1 = n1 - m1;
                m0 = n0;
                m1 = n1;
#pragma unroll
                for (int i = 0; i < 24; i++) s[i] -= (i & 2) ? z1 : z0;
                z0 = ex2(-z0);
                z1 = ex2(-z1);
                l0 *= z0;
                l1 *= z1;
#pragma unroll
                for (int i = 0; i < 116; i++) oa[i] *= (i & 2) ? z1 : z0;
#pragma unroll
                for (int i = 0; i < 12; i++) ob[i] *= (i & 2) ? z1 : z0;
            }
            uint32_t p[12];
#pragma unroll
            for (int i = 5; i >= 0; i--) {
                const float e0 = ex2(s[4 * i]), e1 = ex2(s[4 * i + 1]), e2 = ex2(s[4 * i + 2]), e3 = ex2(s[4 * i + 3]);
                l0 += e0 + e1;
                l1 += e2 + e3;
                p[2 * i] = pack_bf16(e0, e1);
                p[2 * i + 1] = pack_bf16(e2, e3);
            }
            mbar_wait(sb + BAR_FULLKV + slot * 8, use & 1);
            {
                const uint32_t dv = make_desc(sb + SM_RING + slot * KV_TILE, 6144);
                float tb[12];
                fence_regs(oa);
                wgmma_fence();
#pragma unroll
                for (int ks = 0; ks < 3; ks++) {
                    if (ks == 0) wgmma_n24_rs_first(tb, p[0], p[1], p[2], p[3], dv + (VB_OFF >> 4));
                    else wgmma_n24_rs(tb, p[4 * ks], p[4 * ks + 1], p[4 * ks + 2], p[4 * ks + 3], dv + ((ks * 2048 + VB_OFF) >> 4));
                }
#pragma unroll
                for (int ks = 0; ks < 3; ks++)
                    wgmma_n232_rs(oa, p[4 * ks], p[4 * ks + 1], p[4 * ks + 2], p[4 * ks + 3], dv + ((ks * 2048) >> 4));
                wgmma_commit();
                produce(t);
                wgmma_wait<0>();
                fence_regs(oa);
                fence_regs(tb);
                warp_arrive(sb + BAR_EMPTYKV + slot * 8);
#pragma unroll
                for (int i = 0; i < 12; i++) ob[i] += tb[i];
            }
            if (++slot == 5) { slot = 0; use++; }
        }
        if (wg == 0) BAR_SYNC(4, 256);

        l0 += __shfl_xor_sync(0xffffffffu, l0, 1);
        l1 += __shfl_xor_sync(0xffffffffu, l1, 1);
        l0 += __shfl_xor_sync(0xffffffffu, l0, 2);
        l1 += __shfl_xor_sync(0xffffffffu, l1, 2);
        const float i0 = __fdividef(1.f, l0), i1 = __fdividef(1.f, l1);
        const int mi = lane >> 3, r = lane & 7;
        const uint32_t base = sb + SM_Q + (warp * 16 + (mi & 1) * 8 + r) * 128;
        auto ov = [&](int i) { return i < 116 ? oa[i < 116 ? i : 0] : ob[i < 116 ? 0 : i - 116]; };
#pragma unroll
        for (int j = 0; j < 32; j += 2) {
            const uint32_t g = (j & 7) + (mi >> 1);
            stsm4(base + (j >> 3) * 24576 + ((g ^ r) << 4), pack_bf16(ov(4 * j) * i0, ov(4 * j + 1) * i0),
                  pack_bf16(ov(4 * j + 2) * i1, ov(4 * j + 3) * i1), pack_bf16(ov(4 * j + 4) * i0, ov(4 * j + 5) * i0),
                  pack_bf16(ov(4 * j + 6) * i1, ov(4 * j + 7) * i1));
        }
        asm volatile("fence.proxy.async.shared::cta;" ::: "memory");
        __syncwarp();
        warp_arrive(sb + BAR_OREADY + (warp >= 6 ? 8 : 0));
        if (warp == 3) {
#pragma unroll
            for (int t = WO_EVENT + 1; t < NT_KV; t++) {
                mbar_wait(sb + BAR_EMPTYKV + (t % 5) * 8, (t / 5) & 1);
                if (elect_one()) {
                    const int p = (3 * (t - 39) + 1) >> 1;
                    issue_wo(p);
                    if (t & 1) issue_wo(p + 1);
                }
                __syncwarp();
            }
        }
    }

    const int grp = blk * 8 + b;
    uint32_t epoch;
    asm volatile("ld.shared.u32 %0, [%1];" : "=r"(epoch) : "r"(sb + SM_EPOCH));

    const uint32_t tag = epoch & 1;
    constexpr uint32_t LAND = SM_RING + 2 * 16384;
    auto land = [&](int n) { return sb + LAND + (n < 4 ? n * 12288 : (n - 1) * 16384); };
    const uint4* gblk = g_part + (size_t)((grp * 7 + kvh) * 7) * 768;
    auto block_of = [&](int n) { return n < kvh ? n : (n == kvh ? 6 : n - 1); };
    auto fetch = [&](int n) {
        mbar_expect_tx(sb + BAR_FETCH + n * 8, 12288);
        bulk_load(land(n), gblk + block_of(n) * 768, 12288, sb + BAR_FETCH + n * 8);
    };
    float f[24];
#pragma unroll
    for (int e = 0; e < 24; e++) f[e] = 0.f;
#pragma unroll 1
    for (int i = wg; i < 7; i += 3) {
        float acc[48];
        auto release = [&](int p) {
            if (p < 26) {
                if (warp_release(sb + CNT_H + (p & 7) * 4, 1) == 4 * ((p >> 3) + 4) && p < 20) issue_wo(p + 8);
            }
        };
        if (i == 6 && tid == 32) asm volatile("prefetch.tensormap [%0];" ::"l"(&maps.out) : "memory");
        if (i == 6 && warp == 0 && kvh < 7) {
#pragma unroll 1
            for (int n = 0; n < 2; n++) {
                uint32_t c;
                do {
                    asm volatile("ld.volatile.shared.u32 %0, [%1];" : "=r"(c) : "r"(sb + CNT_H + (4 + n) * 4) : "memory");
                } while (c != 24);
                if (elect_one()) fetch(n);
                __syncwarp();
            }
        }
        if (i > 0) BAR_SYNC(bar_me, 256);
#pragma unroll
        for (int qd = 0; qd < 4; qd++) {
            const int p = 4 * i + qd;
            const uint32_t h = (p + 6) & 7;
            if (!(qd & 1)) mbar_wait(sb + BAR_OREADY + (qd >> 1) * 8, 0);
            mbar_wait(sb + BAR_FULLW + (32 + p) * 8, 0);
            const uint32_t da = make_desc(sb + SM_RING + h * 16384, 0);
            const uint32_t db = make_desc(sb + SM_Q + (qd >> 1) * 12288 + (qd & 1) * 2 * 24576, 0);
            wgmma_fence();
#pragma unroll
            for (int ks = 0; ks < 8; ks++) {
                const uint32_t a = da + ((ks * 2048) >> 4);
                const uint32_t bb = db + (((ks >> 2) * 24576 + (ks & 3) * 32) >> 4);
                if (qd == 0 && ks == 0) wgmma_n96_ta_first(acc, a, bb);
                else wgmma_n96_ta(acc, a, bb);
            }
            wgmma_commit();
            if (qd == (i == 5 ? 3 : 2) && i < 6) BAR_ARRIVE(bar_next, 256);
            if (qd > 0) {
                wgmma_wait<1>();
                release(p - 1);
            }
        }
        wgmma_wait<0>();
        fence_regs(acc);
        release(4 * i + 3);
        if (i < 6 || kvh == 7) {
            const int blkid = (grp * 7 + otile(i)) * 7 + (kvh == 7 ? 6 : i);
            uint4* dst = g_part + (size_t)blkid * 768 + (tid & 127);
#pragma unroll
            for (int u = 0; u < 6; u++) {
                const uint32_t xb = __float_as_uint(acc[8 * u]);
                const uint32_t xr = ((min(xb & 0x7fffffffu, 0x7fc00000u) + 0x10000u) & 0x7ffe0000u) | (xb & 0x80000000u);
                st_packet(dst + u * 128, __byte_perm(xr, pack_bf16(0.f, acc[8 * u + 1]), 0x7632) | tag, pack_bf16(acc[8 * u + 2], acc[8 * u + 3]),
                          pack_bf16(acc[8 * u + 4], acc[8 * u + 5]), pack_bf16(acc[8 * u + 6], acc[8 * u + 7]));
            }
            if (lane == 0)
                asm volatile("st.relaxed.gpu.global.u32 [%0], %1;" ::"l"(g_flag + (grp * 7 + otile(i)) * 32 + (kvh == 7 ? 6 : i) * 4 + wi),
                             "r"(epoch) : "memory");
        } else {
            BAR_SYNC(1, 128);
#pragma unroll
            for (int e = 0; e < 24; e++) f[e] = acc[24 + e];
#pragma unroll
            for (int j = 0; j < 6; j++)
                asm volatile("st.shared.v4.f32 [%0], {%1, %2, %3, %4};" ::"r"(sb + SM_RING + (j * 128 + tid) * 16), "f"(acc[4 * j]),
                             "f"(acc[4 * j + 1]), "f"(acc[4 * j + 2]), "f"(acc[4 * j + 3]) : "memory");
            __syncwarp();
            warp_arrive(sb + BAR_ACC);
        }
    }

    if (kvh < 7 && wg == 1) {
        int spins = 0;
#pragma unroll 1
        for (int n = wi == 0 ? 2 : 3 + wi; n < 4 + wi; n++) {
            const int p = n < 2 ? 20 + n : (n < 4 ? 22 : 19 + n);
            uint32_t fl = epoch, c;
            while (n >= 4) {
                if (lane < 4) asm volatile("ld.relaxed.gpu.global.u32 %0, [%1];" : "=r"(fl) : "l"(g_flag + (grp * 7 + kvh) * 32 + block_of(n) * 4 + lane) : "memory");
                if (__all_sync(0xffffffffu, fl == epoch)) break;
                if (++spins > (1 << 21)) __trap();
            }
            do {
                asm volatile("ld.volatile.shared.u32 %0, [%1];" : "=r"(c) : "r"(sb + CNT_H + (p & 7) * 4) : "memory");
            } while (c != 4 * ((p >> 3) + 4));
            if (elect_one()) fetch(n);
            __syncwarp();
        }
    }
    if (kvh < 7 && wg != 1) {
        const int t = tid & 127, u0 = wg == 0 ? 3 : 0;
        auto add_blocks = [&](auto N0, auto N1) {
            constexpr int n0 = decltype(N0)::value, n1 = decltype(N1)::value;
            uint4 v[n1 - n0][3];
#pragma unroll
            for (int n = n0; n < n1; n++) mbar_wait(sb + BAR_FETCH + n * 8, 0);
            uint32_t bad = 0;
#pragma unroll
            for (int n = n0; n < n1; n++) {
#pragma unroll
                for (int u = 0; u < 3; u++) {
                    uint4& w = v[n - n0][u];
                    asm volatile("ld.shared.v4.u32 {%0, %1, %2, %3}, [%4];" : "=r"(w.x), "=r"(w.y), "=r"(w.z), "=r"(w.w)
                                 : "r"(land(n) + ((u0 + u) * 128 + t) * 16) : "memory");
                }
            }
#pragma unroll
            for (int n = n0; n < n1; n++) bad |= (v[n - n0][0].x ^ tag) | (v[n - n0][1].x ^ tag) | (v[n - n0][2].x ^ tag);
            if (__builtin_expect(bad & 1, 0)) {
                int spins = 0;
                do {
                    bad = 0;
#pragma unroll
                    for (int n = n0; n < n1; n++) {
#pragma unroll
                        for (int u = 0; u < 3; u++) {
                            uint4& w = v[n - n0][u];
                            if ((w.x ^ tag) & 1) w = ld_packet(gblk + block_of(n) * 768 + (u0 + u) * 128 + t);
                            bad |= w.x ^ tag;
                        }
                    }
                    if (++spins > (1 << 21)) __trap();
                } while (bad & 1);
            }
#pragma unroll
            for (int n = n0; n < n1; n++) {
#pragma unroll
                for (int u = 0; u < 3; u++) {
                    const uint4& w = v[n - n0][u];
                    const uint32_t vv[4] = {w.x & ~1u, w.y, w.z, w.w};
#pragma unroll
                    for (int e = 0; e < 4; e++) {
                        f[8 * u + 2 * e] += __uint_as_float(vv[e] << 16);
                        f[8 * u + 2 * e + 1] += __uint_as_float(vv[e] & 0xffff0000u);
                    }
                }
            }
        };
        auto add_own = [&]() {
            if (wg > 0) {
                mbar_wait(sb + BAR_ACC, 0);
#pragma unroll
                for (int j = 0; j < 6; j++) {
                    float a0, a1, a2, a3;
                    asm volatile("ld.shared.v4.f32 {%0, %1, %2, %3}, [%4];" : "=f"(a0), "=f"(a1), "=f"(a2), "=f"(a3)
                                 : "r"(sb + SM_RING + ((2 * u0 + j) * 128 + t) * 16) : "memory");
                    f[4 * j] += a0;
                    f[4 * j + 1] += a1;
                    f[4 * j + 2] += a2;
                    f[4 * j + 3] += a3;
                }
            }
        };
        add_blocks(IC<0>{}, IC<4>{});
        add_own();
        add_blocks(IC<4>{}, IC<6>{});
        add_blocks(IC<6>{}, IC<7>{});
        __syncwarp();
        {
            const uint32_t stg = sb + SM_RING + 16384 + (wg == 0 ? 6144 : 0);
            const int mi = lane >> 3, r = lane & 7;
            const uint32_t base = stg + ((mi >> 1) * 8 + r) * 128 + (((2 * wi + (mi & 1)) ^ r) << 4);
#pragma unroll
            for (int j = 0; j < 6; j += 2)
                stsm4_t(base + j * 1024, pack_bf16(f[4 * j], f[4 * j + 1]), pack_bf16(f[4 * j + 2], f[4 * j + 3]),
                        pack_bf16(f[4 * j + 4], f[4 * j + 5]), pack_bf16(f[4 * j + 6], f[4 * j + 7]));
            asm volatile("fence.proxy.async.shared::cta;" ::: "memory");
            BAR_SYNC(wg + 1, 128);
            if (t == 0) {
                asm volatile("cp.async.bulk.tensor.2d.global.shared::cta.bulk_group [%0, {%1, %2}], [%3];"
                             ::"l"(&maps.out), "r"(blk * DM + kvh * 64), "r"(b * SQ + 16 * u0), "r"(stg) : "memory");
                asm volatile("cp.async.bulk.commit_group;" ::: "memory");
                asm volatile("cp.async.bulk.wait_group.read 0;" ::: "memory");
            }
        }
    }
}

typedef CUresult (*EncodeFn)(CUtensorMap*, CUtensorMapDataType, cuuint32_t, void*, const cuuint64_t*, const cuuint64_t*,
                             const cuuint32_t*, const cuuint32_t*, CUtensorMapInterleave, CUtensorMapSwizzle,
                             CUtensorMapL2promotion, CUtensorMapFloatOOBfill);

void encode(EncodeFn fn, CUtensorMap* m, void* ptr, int rank, const cuuint64_t* dims, const cuuint64_t* strides,
            const cuuint32_t* box) {
    const cuuint32_t es[4] = {1, 1, 1, 1};
    fn(m, CU_TENSOR_MAP_DATA_TYPE_BFLOAT16, rank, ptr, dims, strides, box, es, CU_TENSOR_MAP_INTERLEAVE_NONE,
       CU_TENSOR_MAP_SWIZZLE_128B, CU_TENSOR_MAP_L2_PROMOTION_L2_256B, CU_TENSOR_MAP_FLOAT_OOB_FILL_NONE);
}

}

extern "C" void kernel_launch(void* const* d_in, const int* in_sizes, int n_in, void* d_out, int out_size) {
    (void)in_sizes; (void)n_in; (void)out_size;
    void* fnp = nullptr;
    cudaDriverEntryPointQueryResult qr;
    cudaGetDriverEntryPoint("cuTensorMapEncodeTiled", &fnp, cudaEnableDefault, &qr);
    EncodeFn fn = (EncodeFn)fnp;
    Maps maps;
    for (int blk = 0; blk < 2; blk++) {
        void* x = d_in[blk * 5 + 0];
        void* k = d_in[blk * 5 + 1];
        void* v = d_in[blk * 5 + 2];
        void* wq = d_in[blk * 5 + 3];
        void* wo = d_in[blk * 5 + 4];
        maps.kptr[blk] = (const char*)k;
        maps.vptr[blk] = (const char*)v;
        {
            const cuuint64_t dims[3] = {64, 8 * SQ, 7}, str[2] = {DM * 2, 128};
            const cuuint32_t box[3] = {64, SQ, 7};
            encode(fn, &maps.x[blk], x, 3, dims, str, box);
        }
        {
            const cuuint64_t dims[4] = {64, SK, 4, 64}, str[3] = {DH * 2, 128, (cuuint64_t)SK * DH * 2};
            const cuuint32_t box[4] = {64, 48, 4, 1};
            encode(fn, &maps.k[blk], k, 4, dims, str, box);
            encode(fn, &maps.v[blk], v, 4, dims, str, box);
        }
        {
            const cuuint64_t dims[2] = {4096, DM}, str[1] = {4096 * 2};
            const cuuint32_t box[2] = {64, 112};
            encode(fn, &maps.wq[blk], wq, 2, dims, str, box);
        }
        {
            const cuuint64_t dims[2] = {DM, 4096}, str[1] = {DM * 2};
            const cuuint32_t box[2] = {64, 128};
            encode(fn, &maps.wo[blk], wo, 2, dims, str, box);
        }
    }
    {
        const cuuint64_t dims[2] = {2 * DM, 8 * SQ}, str[1] = {2 * DM * 2};
        const cuuint32_t box[2] = {64, 48};
        encode(fn, &maps.out, d_out, 2, dims, str, box);
    }
    cudaFuncSetAttribute(fused_gqa_kernel, cudaFuncAttributeMaxDynamicSharedMemorySize, SMEM_BYTES);
    fused_gqa_kernel<<<128, NTHREADS, SMEM_BYTES, cudaStreamPerThread>>>(maps);
}
```
